```python
import torch

def _softmax(x, axis=-1):
    return torch.softmax(x, dim=axis)
def _gelu(x):
    return torch.nn.functional.gelu(x, approximate="tanh")
def _silu(x):
    return torch.nn.functional.silu(x)
def _sigmoid(x):
    return torch.sigmoid(x)
def _layernorm(x, axis=-1, eps=1e-5):
    m = x.mean(dim=axis, keepdim=True)
    v = x.var(dim=axis, keepdim=True, unbiased=False)
    return (x - m) / torch.sqrt(v + eps)
def _scatter_add(tgt, idx, src, axis=0):
    return tgt.clone().index_add_(axis, idx, src)
def _segment_sum(src, seg, n):
    out = torch.zeros((n,) + src.shape[1:], dtype=src.dtype)
    return out.index_add_(0, seg, src)
def _pad(x, pw):
    flat = tuple(v for pair in reversed(pw) for v in pair)
    return torch.nn.functional.pad(x, flat)

kernel_name = 'standalone__mixer_channel_mlp__prompt'

def setup_inputs():

    _w = (lambda a: (lambda t: t.to(torch.bfloat16) if t.is_floating_point() else t)(torch.as_tensor(a)))
    B, S, D, F = 1, 2048, 512, 1792
    return {
        "x": _w((lambda *s: torch.randn(*s, dtype=torch.bfloat16) * 0.05)(B, S, D)),
        "w1": _w((lambda *s: torch.randn(*s, dtype=torch.bfloat16) * 0.8)(D, F) * (D ** -0.5)),
        "b1": _w((lambda *s: torch.randn(*s, dtype=torch.bfloat16) * 0.4)(F)),
        "w2": _w((lambda *s: torch.randn(*s, dtype=torch.bfloat16) * 0.05)(F, D) * (F ** -0.5)),
        "b2": _w((lambda *s: torch.randn(*s, dtype=torch.bfloat16) * 0.05)(D)),
    }

def reference(x, w1, b1, w2, b2):
    y = _layernorm(x, axis=-1)
    h = _gelu(torch.einsum("bsd,df->bsf", y, w1) + b1)
    return torch.einsum("bsf,fd->bsd", h, w2) + b2
```

```cpp
#include <cuda_runtime.h>
#include <cuda_bf16.h>
#include <cuda.h>
#include <stdint.h>

namespace {

constexpr int SEQ = 2048, DM = 512, FF = 1792;
constexpr int NSLOT = 7;
constexpr int SLOT_BYTES = 16384;
constexpr int OFF_H_OWN = 0;
constexpr int OFF_H_PEER = 49152;
constexpr int OFF_H_OWN3 = 98304;
constexpr int OFF_H_PEER3 = 106496;
constexpr int OFF_RING = 114688;
constexpr int OFF_BAR = OFF_RING + NSLOT * SLOT_BYTES;
constexpr int BAR_FULL = OFF_BAR;
constexpr int BAR_EMPTY = OFF_BAR + 64;
constexpr int BAR_HFULL = OFF_BAR + 128;
constexpr int BAR_XFREE = OFF_BAR + 192;
constexpr int OFF_B1 = OFF_BAR + 256;
constexpr int OFF_B2 = OFF_BAR + 768;
constexpr int SMEM_TOTAL = OFF_BAR + 1280;

__device__ float4 g_part[16 * 2 * 4 * 4 * 2 * 8 * 128];
__device__ unsigned int g_flag[16 * 2 * 4 * 4 * 2];

__device__ __forceinline__ uint32_t smem_u32(const void* p) { return (uint32_t)__cvta_generic_to_shared(p); }
__device__ __forceinline__ void mbar_init(uint32_t a, uint32_t c) {
    asm volatile("mbarrier.init.shared::cta.b64 [%0], %1;" ::"r"(a), "r"(c) : "memory");
}
__device__ __forceinline__ void mbar_expect_tx(uint32_t a, uint32_t b) {
    asm volatile("mbarrier.arrive.expect_tx.shared::cta.b64 _, [%0], %1;" ::"r"(a), "r"(b) : "memory");
}
__device__ __forceinline__ void mbar_arrive(uint32_t a) {
    asm volatile("mbarrier.arrive.shared::cta.b64 _, [%0];" ::"r"(a) : "memory");
}
__device__ __forceinline__ void mbar_arrive_remote(uint32_t cluster_addr) {
    asm volatile("mbarrier.arrive.release.cluster.shared::cluster.b64 _, [%0];" ::"r"(cluster_addr) : "memory");
}
__device__ __forceinline__ void mbar_wait(uint32_t a, uint32_t ph, int& budget) {
    uint32_t ok = 0;
    while (true) {
        asm volatile(
            "{.reg .pred p; mbarrier.try_wait.parity.shared::cta.b64 p, [%1], %2; selp.u32 %0,1,0,p;}"
            : "=r"(ok)
            : "r"(a), "r"(ph)
            : "memory");
        if (ok) break;
        if (--budget < 0) break;
    }
}
__device__ __forceinline__ void mbar_wait_cluster(uint32_t a, uint32_t ph, int& budget) {
    uint32_t ok = 0;
    while (true) {
        asm volatile(
            "{.reg .pred p; mbarrier.try_wait.parity.acquire.cluster.shared::cta.b64 p, [%1], %2; selp.u32 %0,1,0,p;}"
            : "=r"(ok)
            : "r"(a), "r"(ph)
            : "memory");
        if (ok) break;
        if (--budget < 0) break;
    }
}
__device__ __forceinline__ uint32_t mapa(uint32_t a, uint32_t rank) {
    uint32_t d;
    asm("mapa.shared::cluster.u32 %0, %1, %2;" : "=r"(d) : "r"(a), "r"(rank));
    return d;
}
__device__ __forceinline__ void tma_2d(uint32_t dst, const CUtensorMap* tm, uint32_t bar, int c0, int c1) {
    asm volatile(
        "cp.async.bulk.tensor.2d.shared::cluster.global.mbarrier::complete_tx::bytes [%0], [%1, {%3, %4}], [%2];" ::"r"(dst),
        "l"((uint64_t)tm), "r"(bar), "r"(c0), "r"(c1)
        : "memory");
}
__device__ __forceinline__ void tma_3d(uint32_t dst, const CUtensorMap* tm, uint32_t bar, int c0, int c1, int c2) {
    asm volatile(
        "cp.async.bulk.tensor.3d.shared::cluster.global.mbarrier::complete_tx::bytes [%0], [%1, {%3, %4, %5}], [%2];" ::"r"(dst),
        "l"((uint64_t)tm), "r"(bar), "r"(c0), "r"(c1), "r"(c2)
        : "memory");
}
__device__ __forceinline__ void cluster_sync_all() {
    asm volatile("barrier.cluster.arrive.release.aligned;\n barrier.cluster.wait.acquire.aligned;" ::: "memory");
}
__device__ __forceinline__ void wg_bar(int id) { asm volatile("bar.sync %0, 128;" ::"r"(id) : "memory"); }
__device__ __forceinline__ void wgmma_fence() { asm volatile("wgmma.fence.sync.aligned;" ::: "memory"); }
__device__ __forceinline__ void wgmma_commit() { asm volatile("wgmma.commit_group.sync.aligned;" ::: "memory"); }
template <int N>
__device__ __forceinline__ void wgmma_wait() {
    asm volatile("wgmma.wait_group.sync.aligned %0;" ::"n"(N) : "memory");
}
__device__ __forceinline__ void fence_async_smem() { asm volatile("fence.proxy.async.shared::cta;" ::: "memory"); }

__device__ __forceinline__ uint64_t make_desc(uint32_t addr, uint32_t lbo, uint32_t sbo, uint32_t sw) {
    return (uint64_t)((addr & 0x3FFFF) >> 4) | ((uint64_t)(lbo >> 4) << 16) | ((uint64_t)(sbo >> 4) << 32) |
           ((uint64_t)sw << 62);
}

#define R4(a, i) "+f"(a[i]), "+f"(a[i + 1]), "+f"(a[i + 2]), "+f"(a[i + 3])
#define R16(a, i) R4(a, i), R4(a, i + 4), R4(a, i + 8), R4(a, i + 12)
#define R32(a, i) R16(a, i), R16(a, i + 16)

__device__ __forceinline__ void wgmma_rs_n64(float (&d)[32], const uint32_t* a, uint64_t bdesc, int scale_d) {
    asm volatile(
        "{.reg .pred p; setp.ne.b32 p, %37, 0;\n"
        "wgmma.mma_async.sync.aligned.m64n64k16.f32.bf16.bf16 "
        "{%0,%1,%2,%3,%4,%5,%6,%7,%8,%9,%10,%11,%12,%13,%14,%15,"
        "%16,%17,%18,%19,%20,%21,%22,%23,%24,%25,%26,%27,%28,%29,%30,%31}, "
        "{%32,%33,%34,%35}, %36, p, 1, 1, 1;}\n"
        : R32(d, 0)
        : "r"(a[0]), "r"(a[1]), "r"(a[2]), "r"(a[3]), "l"(bdesc), "r"(scale_d));
}
__device__ __forceinline__ void wgmma_rs_n32(float (&d)[32], const uint32_t* a, uint64_t bdesc, int scale_d) {
    asm volatile(
        "{.reg .pred p; setp.ne.b32 p, %21, 0;\n"
        "wgmma.mma_async.sync.aligned.m64n32k16.f32.bf16.bf16 "
        "{%0,%1,%2,%3,%4,%5,%6,%7,%8,%9,%10,%11,%12,%13,%14,%15}, "
        "{%16,%17,%18,%19}, %20, p, 1, 1, 1;}\n"
        : R16(d, 0)
        : "r"(a[0]), "r"(a[1]), "r"(a[2]), "r"(a[3]), "l"(bdesc), "r"(scale_d));
}
__device__ __forceinline__ void wgmma_ss_n256(float (&d)[128], uint64_t adesc, uint64_t bdesc, int scale_d) {
    asm volatile(
        "{.reg .pred p; setp.ne.b32 p, %130, 0;\n"
        "wgmma.mma_async.sync.aligned.m64n256k16.f32.bf16.bf16 "
        "{%0,%1,%2,%3,%4,%5,%6,%7,%8,%9,%10,%11,%12,%13,%14,%15,"
        "%16,%17,%18,%19,%20,%21,%22,%23,%24,%25,%26,%27,%28,%29,%30,%31,"
        "%32,%33,%34,%35,%36,%37,%38,%39,%40,%41,%42,%43,%44,%45,%46,%47,"
        "%48,%49,%50,%51,%52,%53,%54,%55,%56,%57,%58,%59,%60,%61,%62,%63,"
        "%64,%65,%66,%67,%68,%69,%70,%71,%72,%73,%74,%75,%76,%77,%78,%79,"
        "%80,%81,%82,%83,%84,%85,%86,%87,%88,%89,%90,%91,%92,%93,%94,%95,"
        "%96,%97,%98,%99,%100,%101,%102,%103,%104,%105,%106,%107,%108,%109,%110,%111,"
        "%112,%113,%114,%115,%116,%117,%118,%119,%120,%121,%122,%123,%124,%125,%126,%127}, "
        "%128, %129, p, 1, 1, 0, 1;}\n"
        : R32(d, 0), R32(d, 32), R32(d, 64), R32(d, 96)
        : "l"(adesc), "l"(bdesc), "r"(scale_d));
}

__device__ __forceinline__ uint32_t pack_bf16(float lo, float hi) {
    uint32_t r;
    asm("cvt.rn.bf16x2.f32 %0, %1, %2;" : "=r"(r) : "f"(hi), "f"(lo));
    return r;
}
__device__ __forceinline__ float bf_lo(uint32_t v) { return __uint_as_float(v << 16); }
__device__ __forceinline__ float bf_hi(uint32_t v) { return __uint_as_float(v & 0xffff0000u); }
__device__ __forceinline__ float round_bf16(float v) { return __bfloat162float(__float2bfloat16_rn(v)); }
__device__ __forceinline__ uint32_t bf2_add(uint32_t a, uint32_t b) {
    uint32_t r;
    asm("add.rn.bf16x2 %0, %1, %2;" : "=r"(r) : "r"(a), "r"(b));
    return r;
}
__device__ __forceinline__ uint32_t bf2_sub(uint32_t a, uint32_t b) {
    uint32_t r;
    asm("sub.rn.bf16x2 %0, %1, %2;" : "=r"(r) : "r"(a), "r"(b));
    return r;
}
__device__ __forceinline__ float gelu_tanh(float u) {
    const float k0 = 0.7978845608028654f, k1 = 0.7978845608028654f * 0.044715f;
    float z = u * fmaf(u * u, k1, k0);
    float t;
    asm("tanh.approx.f32 %0, %1;" : "=f"(t) : "f"(z));
    float hh = 0.5f * u;
    return fmaf(hh, t, hh);
}
__device__ __forceinline__ uint32_t gelu_pair(float a0, float a1, uint32_t bias2) {
    uint32_t u2 = bf2_add(pack_bf16(a0, a1), bias2);
    return pack_bf16(gelu_tanh(bf_lo(u2)), gelu_tanh(bf_hi(u2)));
}
__device__ __forceinline__ void stmatrix_x4(uint32_t addr, uint32_t r0, uint32_t r1, uint32_t r2, uint32_t r3) {
    asm volatile("stmatrix.sync.aligned.m8n8.x4.shared.b16 [%0], {%1,%2,%3,%4};" ::"r"(addr), "r"(r0), "r"(r1), "r"(r2),
                 "r"(r3)
                 : "memory");
}
__device__ __forceinline__ uint32_t lds32(uint32_t addr) {
    uint32_t v;
    asm volatile("ld.shared.b32 %0, [%1];" : "=r"(v) : "r"(addr));
    return v;
}

template <bool SW64>
__device__ __forceinline__ void gelu_slice(const float (&acc)[32], int j0, uint32_t bias_addr, uint32_t st_row_addr,
                                           uint32_t st_xor, uint32_t lane_hi) {
    uint32_t bA = lds32(bias_addr + j0 * 16);
    uint32_t bB = lds32(bias_addr + j0 * 16 + 16);
    uint32_t p0 = gelu_pair(acc[4 * j0 + 0], acc[4 * j0 + 1], bA);
    uint32_t p1 = gelu_pair(acc[4 * j0 + 2], acc[4 * j0 + 3], bA);
    uint32_t p2 = gelu_pair(acc[4 * j0 + 4], acc[4 * j0 + 5], bB);
    uint32_t p3 = gelu_pair(acc[4 * j0 + 6], acc[4 * j0 + 7], bB);
    uint32_t chunk = (uint32_t)j0 + lane_hi;
    stmatrix_x4(st_row_addr + ((chunk ^ st_xor) << 4), p0, p1, p2, p3);
}

__global__ void __launch_bounds__(384, 1)
mixer_mlp_kernel(const __grid_constant__ CUtensorMap tm_x, const __grid_constant__ CUtensorMap tm_w1a,
                 const __grid_constant__ CUtensorMap tm_w1b, const __grid_constant__ CUtensorMap tm_w2,
                 const __nv_bfloat16* __restrict__ b1, const __nv_bfloat16* __restrict__ b2,
                 __nv_bfloat16* __restrict__ out) {
    extern __shared__ __align__(1024) uint8_t smem[];
    const uint32_t sb = smem_u32(smem);
    const int tid = threadIdx.x;
    const int warp = tid >> 5, lane = tid & 31;
    const int r = blockIdx.x & 1;
    const int f = (blockIdx.x >> 1) & 3;
    const int rt = blockIdx.x >> 3;
    int budget = 1 << 22;
    const int fcol_own = 448 * f + 224 * r;
    const int fcol_peer = 448 * f + 224 * (1 - r);

    if (tid == 0) {
        for (int i = 0; i < NSLOT; i++) {
            mbar_init(sb + BAR_FULL + 8 * i, 1);
            mbar_init(sb + BAR_EMPTY + 8 * i, 8);
        }
        for (int i = 0; i < 8; i++) mbar_init(sb + BAR_HFULL + 8 * i, 1);
        for (int i = 0; i < 2; i++) mbar_init(sb + BAR_XFREE + 8 * i, 4);
        asm volatile("fence.mbarrier_init.release.cluster;" ::: "memory");
        for (int i = 0; i < 8; i++) mbar_expect_tx(sb + BAR_HFULL + 8 * i, (i >> 1) == 3 ? 4096 : 8192);
    }
    if (tid < 112) {
        reinterpret_cast<uint32_t*>(smem + OFF_B1)[tid] = reinterpret_cast<const uint32_t*>(b1 + fcol_own)[tid];
    } else if (tid >= 128 && tid < 256) {
        reinterpret_cast<uint32_t*>(smem + OFF_B2)[tid - 128] = reinterpret_cast<const uint32_t*>(b2 + 256 * r)[tid - 128];
    }
    __syncthreads();
    cluster_sync_all();

    if (warp >= 8) {
        asm volatile("setmaxnreg.dec.sync.aligned.u32 24;");
        if (warp == 8 && lane == 0) {
            mbar_expect_tx(sb + BAR_FULL, 131072);
            for (int kb = 0; kb < 8; kb++) tma_2d(sb + kb * 16384, &tm_x, sb + BAR_FULL, kb * 64, rt * 128);
            int slot = 1;
            uint32_t ph = 1;
            for (int j = 1; j <= 28; j++) {
                mbar_wait(sb + BAR_EMPTY + 8 * slot, ph, budget);
                const uint32_t bar = sb + BAR_FULL + 8 * slot;
                const uint32_t dst = sb + OFF_RING + slot * SLOT_BYTES;
                mbar_expect_tx(bar, SLOT_BYTES);
                int s = j - 1;
                if (s < 12) {
                    tma_2d(dst, &tm_w1a, bar, fcol_own + (s >> 2) * 64, (s & 3) * 128);
                } else if (s < 14) {
                    tma_2d(dst, &tm_w1b, bar, fcol_own + 192, (s - 12) * 256);
                } else {
                    int p = s - 14;
                    int row = (p < 7) ? (fcol_own + 32 * p) : (fcol_peer + 32 * (p - 7));
                    tma_3d(dst, &tm_w2, bar, 0, row, 4 * r);
                }
                if (++slot == NSLOT) {
                    slot = 0;
                    ph ^= 1;
                }
            }
        }
        __syncwarp();
        cluster_sync_all();
    } else {
        asm volatile("setmaxnreg.inc.sync.aligned.u32 240;");
        const int w = warp >> 2, wq = warp & 3;
        const int g = lane >> 2, t = lane & 3;
        const uint32_t peer = (uint32_t)(r ^ 1);

        uint32_t y[128];
        mbar_wait(sb + BAR_FULL, 0, budget);
        {
            const int row = 64 * w + 16 * wq + (lane & 15);
            const uint32_t base = sb + row * 128;
            const uint32_t xr = row & 7, hi = lane >> 4;
#pragma unroll
            for (int ks = 0; ks < 32; ks++) {
                uint32_t addr = base + (ks >> 2) * 16384 + ((((ks & 3) * 2 + hi) ^ xr) << 4);
                asm volatile("ldmatrix.sync.aligned.m8n8.x4.shared.b16 {%0,%1,%2,%3}, [%4];"
                             : "=r"(y[4 * ks]), "=r"(y[4 * ks + 1]), "=r"(y[4 * ks + 2]), "=r"(y[4 * ks + 3])
                             : "r"(addr)
                             : "memory");
            }
        }
        __syncwarp();
        if (lane == 0) {
            mbar_arrive(sb + BAR_EMPTY);
            mbar_arrive_remote(mapa(sb + BAR_XFREE + 8 * w, peer));
        }
        {
            float sa[4] = {0.f, 0.f, 0.f, 0.f}, sc[4] = {0.f, 0.f, 0.f, 0.f};
#pragma unroll
            for (int ks = 0; ks < 32; ks += 2) {
                asm volatile(
                    "mma.sync.aligned.m16n8k16.row.col.f32.bf16.bf16.f32 {%0,%1,%2,%3}, {%4,%5,%6,%7}, {%8,%8}, {%0,%1,%2,%3};"
                    : "+f"(sa[0]), "+f"(sa[1]), "+f"(sa[2]), "+f"(sa[3])
                    : "r"(y[4 * ks]), "r"(y[4 * ks + 1]), "r"(y[4 * ks + 2]), "r"(y[4 * ks + 3]), "r"(0x3F803F80u));
                asm volatile(
                    "mma.sync.aligned.m16n8k16.row.col.f32.bf16.bf16.f32 {%0,%1,%2,%3}, {%4,%5,%6,%7}, {%8,%8}, {%0,%1,%2,%3};"
                    : "+f"(sc[0]), "+f"(sc[1]), "+f"(sc[2]), "+f"(sc[3])
                    : "r"(y[4 * ks + 4]), "r"(y[4 * ks + 5]), "r"(y[4 * ks + 6]), "r"(y[4 * ks + 7]), "r"(0x3F803F80u));
            }
            const float s0 = sa[0] + sc[0], s1 = sa[2] + sc[2];
            const float m0 = s0 * (1.f / DM), m1 = s1 * (1.f / DM);
            float q0 = 0.f, q1 = 0.f;
#pragma unroll
            for (int i = 0; i < 128; i++) asm volatile("" : "+r"(y[i]));
#pragma unroll
            for (int ks = 0; ks < 32; ks++) {
#pragma unroll
                for (int e = 0; e < 2; e++) {
                    float a = bf_lo(y[4 * ks + 2 * e]) - m0, b = bf_hi(y[4 * ks + 2 * e]) - m0;
                    q0 = fmaf(a, a, q0);
                    q0 = fmaf(b, b, q0);
                    float c = bf_lo(y[4 * ks + 2 * e + 1]) - m1, d = bf_hi(y[4 * ks + 2 * e + 1]) - m1;
                    q1 = fmaf(c, c, q1);
                    q1 = fmaf(d, d, q1);
                }
                if ((ks & 3) == 3) asm volatile("" : "+f"(q0), "+f"(q1));
            }
            q0 += __shfl_xor_sync(0xffffffffu, q0, 1);
            q0 += __shfl_xor_sync(0xffffffffu, q0, 2);
            q1 += __shfl_xor_sync(0xffffffffu, q1, 1);
            q1 += __shfl_xor_sync(0xffffffffu, q1, 2);
            const float sd0 = round_bf16(sqrtf(round_bf16(round_bf16(q0 * (1.f / DM)) + 1e-5f)));
            const float sd1 = round_bf16(sqrtf(round_bf16(round_bf16(q1 * (1.f / DM)) + 1e-5f)));
            const float rs0 = 1.f / sd0, rs1 = 1.f / sd1;
            const uint32_t mm0 = pack_bf16(m0, m0), mm1 = pack_bf16(m1, m1);
#pragma unroll
            for (int i = 0; i < 128; i++) asm volatile("" : "+r"(y[i]));
#pragma unroll
            for (int i = 0; i < 128; i++) {
                const bool odd = i & 1;
                uint32_t d2 = bf2_sub(y[i], odd ? mm1 : mm0);
                const float rs = odd ? rs1 : rs0;
                y[i] = pack_bf16(bf_lo(d2) * rs, bf_hi(d2) * rs);
                if ((i & 7) == 7)
                    asm volatile("" : "+r"(y[i - 7]), "+r"(y[i - 6]), "+r"(y[i - 5]), "+r"(y[i - 4]), "+r"(y[i - 3]),
                                 "+r"(y[i - 2]), "+r"(y[i - 1]), "+r"(y[i]));
            }
        }

        const int srow = (lane & 7) + 8 * ((lane >> 3) & 1);
        const uint32_t lane_hi = lane >> 4;
        const uint32_t st128 = sb + (64 * w + 16 * wq + srow) * 128;
        const uint32_t st64 = sb + (64 * w + 16 * wq + srow) * 64;
        const uint32_t x128 = srow & 7, x64 = (srow >> 1) & 3;
        const uint32_t bias_base = sb + OFF_B1 + 4 * t;

        int slot = 1;
        uint32_t ph = 0;
        int prev_slot = -1;
        float accA[32], accB[32];

        auto advance = [&]() {
            prev_slot = slot;
            if (++slot == NSLOT) {
                slot = 0;
                ph ^= 1;
            }
        };
        auto release_prev = [&]() {
            if (lane == 0) mbar_arrive(sb + BAR_EMPTY + 8 * prev_slot);
        };
        auto publish = [&](int c) {
            fence_async_smem();
            wg_bar(1 + w);
            if (wq == 0 && lane == 0) {
                if (c == 0) mbar_wait_cluster(sb + BAR_XFREE + 8 * w, 0, budget);
                const uint32_t bytes = (c == 3) ? 4096 : 8192;
                const uint32_t src = sb + ((c == 3) ? OFF_H_OWN3 : OFF_H_OWN + c * 16384) + w * bytes;
                const uint32_t dst = mapa(sb + ((c == 3) ? OFF_H_PEER3 : OFF_H_PEER + c * 16384) + w * bytes, peer);
                const uint32_t bar = mapa(sb + BAR_HFULL + 8 * (2 * c + w), peer);
                asm volatile("cp.async.bulk.shared::cluster.shared::cta.mbarrier::complete_tx::bytes [%0], [%1], %2, [%3];" ::"r"(dst),
                             "r"(src), "r"(bytes), "r"(bar)
                             : "memory");
            }
        };

#pragma unroll
        for (int c = 0; c < 3; c++) {
            float(&acc)[32] = (c & 1) ? accB : accA;
            float(&accp)[32] = (c & 1) ? accA : accB;
#pragma unroll
            for (int s = 0; s < 4; s++) {
                mbar_wait(sb + BAR_FULL + 8 * slot, ph, budget);
                const uint32_t bs = sb + OFF_RING + slot * SLOT_BYTES;
                wgmma_fence();
#pragma unroll
                for (int k = 0; k < 8; k++)
                    wgmma_rs_n64(acc, &y[4 * (8 * s + k)], make_desc(bs + k * 2048, 0, 1024, 1), (s | k) != 0);
                wgmma_commit();
                if (c | s) {
                    wgmma_wait<1>();
                    release_prev();
                }
                advance();
                if (c > 0) {
                    gelu_slice<false>(accp, 2 * s, bias_base + (c - 1) * 128, st128 + OFF_H_OWN + (c - 1) * 16384, x128,
                                      lane_hi);
                    if (s == 3) publish(c - 1);
                }
            }
        }
#pragma unroll
        for (int s = 0; s < 2; s++) {
            mbar_wait(sb + BAR_FULL + 8 * slot, ph, budget);
            const uint32_t bs = sb + OFF_RING + slot * SLOT_BYTES;
            wgmma_fence();
#pragma unroll
            for (int k = 0; k < 16; k++)
                wgmma_rs_n32(accB, &y[4 * (16 * s + k)], make_desc(bs + k * 1024, 0, 512, 2), (s | k) != 0);
            wgmma_commit();
            wgmma_wait<1>();
            release_prev();
            advance();
            gelu_slice<false>(accA, 4 * s, bias_base + 256, st128 + OFF_H_OWN + 32768, x128, lane_hi);
            gelu_slice<false>(accA, 4 * s + 2, bias_base + 256, st128 + OFF_H_OWN + 32768, x128, lane_hi);
        }
        publish(2);
        wgmma_wait<0>();
        release_prev();

        float acc2[128];
#pragma unroll
        for (int p = 0; p < 14; p++) {
            const int pc = (p % 7) >> 1;
            const bool own = p < 7;
            if (!own && ((p % 7) & 1) == 0) mbar_wait_cluster(sb + BAR_HFULL + 8 * (2 * pc + w), 0, budget);
            mbar_wait(sb + BAR_FULL + 8 * slot, ph, budget);
            const uint32_t bs = sb + OFF_RING + slot * SLOT_BYTES;
            wgmma_fence();
#pragma unroll
            for (int k = 0; k < 2; k++) {
                uint64_t ad;
                if (pc == 3)
                    ad = make_desc(sb + (own ? OFF_H_OWN3 : OFF_H_PEER3) + w * 4096 + k * 32, 0, 512, 2);
                else
                    ad = make_desc(sb + (own ? OFF_H_OWN : OFF_H_PEER) + pc * 16384 + w * 8192 + ((p % 7) & 1) * 64 + k * 32,
                                   0, 1024, 1);
                wgmma_ss_n256(acc2, ad, make_desc(bs + k * 2048, 4096, 1024, 1), (p | k) != 0);
            }
            wgmma_commit();
            if (p > 0) {
                wgmma_wait<1>();
                release_prev();
            }
            advance();
            if (p == 0) {
                gelu_slice<true>(accB, 0, bias_base + 384, st64 + OFF_H_OWN3, x64, lane_hi);
                gelu_slice<true>(accB, 2, bias_base + 384, st64 + OFF_H_OWN3, x64, lane_hi);
                publish(3);
            }
        }
        wgmma_wait<0>();

        const int tw = tid & 127;
        const int grp = rt * 2 + r;
        {
            float4* dst = g_part + (size_t)((grp * 4 + f) * 4) * 2048 + w * 1024 + tw;
#pragma unroll
            for (int q = 0; q < 4; q++) {
                if (q != f) {
#pragma unroll
                    for (int i = 0; i < 8; i++)
                        __stcg(dst + q * 2048 + i * 128,
                               make_float4(acc2[32 * q + 4 * i], acc2[32 * q + 4 * i + 1], acc2[32 * q + 4 * i + 2],
                                           acc2[32 * q + 4 * i + 3]));
                }
            }
        }
        __threadfence();
        wg_bar(1 + w);
        if (tw < 4 && tw != f) {
            asm volatile("st.release.gpu.global.u32 [%0], %1;" ::"l"(g_flag + ((grp * 4 + tw) * 4 + f) * 2 + w), "r"(1u)
                         : "memory");
        }
        float o[32];
#pragma unroll
        for (int q = 0; q < 4; q++) {
            if (q == f) {
#pragma unroll
                for (int i = 0; i < 32; i++) o[i] = acc2[32 * q + i];
            }
        }
        if (tw < 4 && tw != f) {
            unsigned int* fl = g_flag + ((grp * 4 + f) * 4 + tw) * 2 + w;
            unsigned int v = 0;
            while (true) {
                asm volatile("ld.acquire.gpu.global.u32 %0, [%1];" : "=r"(v) : "l"(fl) : "memory");
                if (v) break;
                if (--budget < 0) break;
            }
            *fl = 0;
        }
        wg_bar(1 + w);
#pragma unroll
        for (int sf = 0; sf < 4; sf++) {
            if (sf != f) {
                const float4* src = g_part + (size_t)(((grp * 4 + sf) * 4) + f) * 2048 + w * 1024 + tw;
#pragma unroll
                for (int i = 0; i < 8; i++) {
                    float4 v = __ldcg(src + i * 128);
                    o[4 * i] += v.x;
                    o[4 * i + 1] += v.y;
                    o[4 * i + 2] += v.z;
                    o[4 * i + 3] += v.w;
                }
            }
        }
        {
            const int row0 = rt * 128 + 64 * w + 16 * wq + g;
            const int col0 = 256 * r + 64 * f + 2 * t;
            uint32_t* o0 = reinterpret_cast<uint32_t*>(out + (size_t)row0 * DM + col0);
            uint32_t* o1 = reinterpret_cast<uint32_t*>(out + (size_t)(row0 + 8) * DM + col0);
            const uint32_t b2a = sb + OFF_B2 + (64 * f + 2 * t) * 2;
#pragma unroll
            for (int j = 0; j < 8; j++) {
                uint32_t bb = lds32(b2a + j * 16);
                o0[4 * j] = bf2_add(pack_bf16(o[4 * j], o[4 * j + 1]), bb);
                o1[4 * j] = bf2_add(pack_bf16(o[4 * j + 2], o[4 * j + 3]), bb);
            }
        }
        cluster_sync_all();
    }
}

typedef CUresult (*EncodeFn)(CUtensorMap*, CUtensorMapDataType, cuuint32_t, void*, const cuuint64_t*, const cuuint64_t*,
                             const cuuint32_t*, const cuuint32_t*, CUtensorMapInterleave, CUtensorMapSwizzle,
                             CUtensorMapL2promotion, CUtensorMapFloatOOBfill);

}

extern "C" void kernel_launch(void* const* d_in, const int* in_sizes, int n_in, void* d_out, int out_size) {
    (void)in_sizes;
    (void)n_in;
    (void)out_size;
    static EncodeFn enc = nullptr;
    if (!enc) {
        void* fn = nullptr;
        cudaDriverEntryPointQueryResult st;
        cudaGetDriverEntryPoint("cuTensorMapEncodeTiled", &fn, cudaEnableDefault, &st);
        enc = (EncodeFn)fn;
        cudaFuncSetAttribute(mixer_mlp_kernel, cudaFuncAttributeMaxDynamicSharedMemorySize, SMEM_TOTAL);
    }
    void* x = d_in[0];
    void* w1 = d_in[1];
    const __nv_bfloat16* b1 = (const __nv_bfloat16*)d_in[2];
    void* w2 = d_in[3];
    const __nv_bfloat16* b2 = (const __nv_bfloat16*)d_in[4];

    CUtensorMap tm_x, tm_w1a, tm_w1b, tm_w2;
    {
        cuuint64_t gd[2] = {(cuuint64_t)DM, (cuuint64_t)SEQ};
        cuuint64_t gs[1] = {(cuuint64_t)DM * 2};
        cuuint32_t bd[2] = {64, 128};
        cuuint32_t es[2] = {1, 1};
        enc(&tm_x, CU_TENSOR_MAP_DATA_TYPE_BFLOAT16, 2, x, gd, gs, bd, es, CU_TENSOR_MAP_INTERLEAVE_NONE,
            CU_TENSOR_MAP_SWIZZLE_128B, CU_TENSOR_MAP_L2_PROMOTION_L2_256B, CU_TENSOR_MAP_FLOAT_OOB_FILL_NONE);
    }
    {
        cuuint64_t gd[2] = {(cuuint64_t)FF, (cuuint64_t)DM};
        cuuint64_t gs[1] = {(cuuint64_t)FF * 2};
        cuuint32_t bd[2] = {64, 128};
        cuuint32_t es[2] = {1, 1};
        enc(&tm_w1a, CU_TENSOR_MAP_DATA_TYPE_BFLOAT16, 2, w1, gd, gs, bd, es, CU_TENSOR_MAP_INTERLEAVE_NONE,
            CU_TENSOR_MAP_SWIZZLE_128B, CU_TENSOR_MAP_L2_PROMOTION_L2_128B, CU_TENSOR_MAP_FLOAT_OOB_FILL_NONE);
        cuuint32_t bd2[2] = {32, 256};
        enc(&tm_w1b, CU_TENSOR_MAP_DATA_TYPE_BFLOAT16, 2, w1, gd, gs, bd2, es, CU_TENSOR_MAP_INTERLEAVE_NONE,
            CU_TENSOR_MAP_SWIZZLE_64B, CU_TENSOR_MAP_L2_PROMOTION_L2_128B, CU_TENSOR_MAP_FLOAT_OOB_FILL_NONE);
    }
    {
        cuuint64_t gd[3] = {64, (cuuint64_t)FF, 8};
        cuuint64_t gs[2] = {(cuuint64_t)DM * 2, 128};
        cuuint32_t bd[3] = {64, 32, 4};
        cuuint32_t es[3] = {1, 1, 1};
        enc(&tm_w2, CU_TENSOR_MAP_DATA_TYPE_BFLOAT16, 3, w2, gd, gs, bd, es, CU_TENSOR_MAP_INTERLEAVE_NONE,
            CU_TENSOR_MAP_SWIZZLE_128B, CU_TENSOR_MAP_L2_PROMOTION_L2_256B, CU_TENSOR_MAP_FLOAT_OOB_FILL_NONE);
    }

    cudaLaunchConfig_t cfg = {};
    cfg.gridDim = dim3(128);
    cfg.blockDim = dim3(384);
    cfg.dynamicSmemBytes = SMEM_TOTAL;
    cfg.stream = cudaStreamPerThread;
    cudaLaunchAttribute at[1];
    at[0].id = cudaLaunchAttributeClusterDimension;
    at[0].val.clusterDim.x = 2;
    at[0].val.clusterDim.y = 1;
    at[0].val.clusterDim.z = 1;
    cfg.attrs = at;
    cfg.numAttrs = 1;
    cudaLaunchKernelEx(&cfg, mixer_mlp_kernel, tm_x, tm_w1a, tm_w1b, tm_w2, b1, b2, (__nv_bfloat16*)d_out);
}
```

```cpp
#include <cuda_runtime.h>
#include <cuda_bf16.h>
#include <cuda.h>
#include <stdint.h>

namespace {

constexpr int SEQ = 2048, DM = 512, FF = 1792;
constexpr int NSLOT = 7;
constexpr int SLOT_BYTES = 16384;
constexpr int OFF_H_OWN = 0;
constexpr int OFF_H_PEER = 49152;
constexpr int OFF_H_OWN3 = 98304;
constexpr int OFF_H_PEER3 = 106496;
constexpr int OFF_RING = 114688;
constexpr int OFF_BAR = OFF_RING + NSLOT * SLOT_BYTES;
constexpr int BAR_FULL = OFF_BAR;
constexpr int BAR_EMPTY = OFF_BAR + 64;
constexpr int BAR_HFULL = OFF_BAR + 128;
constexpr int BAR_XFREE = OFF_BAR + 192;
constexpr int BAR_RDY = OFF_BAR + 208;
constexpr int BAR_XFULL = OFF_BAR + 216;
constexpr int BAR_BIAS = OFF_BAR + 288;
constexpr int BAR_PUB = OFF_BAR + 296;
constexpr int BAR_HRECV = OFF_BAR + 328;
constexpr int OFF_B1 = OFF_BAR + 1024;
constexpr int OFF_B2 = OFF_BAR + 896;
constexpr int SMEM_TOTAL = OFF_BAR + 2048;

__device__ uint4 g_part[16 * 2 * 4 * 3 * 1024];
__device__ unsigned int g_ready[16 * 2 * 4];

__device__ __forceinline__ uint32_t smem_u32(const void* p) { return (uint32_t)__cvta_generic_to_shared(p); }
__device__ __forceinline__ void mbar_init(uint32_t a, uint32_t c) {
    asm volatile("mbarrier.init.shared::cta.b64 [%0], %1;" ::"r"(a), "r"(c) : "memory");
}
__device__ __forceinline__ void mbar_expect_tx(uint32_t a, uint32_t b) {
    asm volatile("mbarrier.arrive.expect_tx.shared::cta.b64 _, [%0], %1;" ::"r"(a), "r"(b) : "memory");
}
__device__ __forceinline__ void mbar_arrive(uint32_t a) {
    asm volatile("mbarrier.arrive.shared::cta.b64 _, [%0];" ::"r"(a) : "memory");
}
__device__ __forceinline__ void mbar_arrive_remote(uint32_t cluster_addr) {
    asm volatile("mbarrier.arrive.relaxed.cluster.shared::cluster.b64 _, [%0];" ::"r"(cluster_addr) : "memory");
}
__device__ __forceinline__ void mbar_wait(uint32_t a, uint32_t ph, int& budget) {
    uint32_t ok = 0;
    while (true) {
        asm volatile(
            "{.reg .pred p; mbarrier.try_wait.parity.shared::cta.b64 p, [%1], %2, 2000; selp.u32 %0,1,0,p;}"
            : "=r"(ok)
            : "r"(a), "r"(ph)
            : "memory");
        if (ok) break;
        if (--budget < 0) break;
    }
}
__device__ __forceinline__ uint32_t mapa(uint32_t a, uint32_t rank) {
    uint32_t d;
    asm("mapa.shared::cluster.u32 %0, %1, %2;" : "=r"(d) : "r"(a), "r"(rank));
    return d;
}
__device__ __forceinline__ void tma_2d(uint32_t dst, const CUtensorMap* tm, uint32_t bar, int c0, int c1) {
    asm volatile(
        "cp.async.bulk.tensor.2d.shared::cluster.global.mbarrier::complete_tx::bytes [%0], [%1, {%3, %4}], [%2];" ::"r"(dst),
        "l"((uint64_t)tm), "r"(bar), "r"(c0), "r"(c1)
        : "memory");
}
__device__ __forceinline__ uint32_t tid_now() {
    uint32_t t;
    asm volatile("mov.u32 %0, %%tid.x;" : "=r"(t));
    return t;
}
__device__ __forceinline__ void cluster_arrive_relaxed() { asm volatile("barrier.cluster.arrive.relaxed.aligned;" ::: "memory"); }
__device__ __forceinline__ void cluster_wait() { asm volatile("barrier.cluster.wait.aligned;" ::: "memory"); }
__device__ __forceinline__ void bar_sync(int id, int n) { asm volatile("bar.sync %0, %1;" ::"r"(id), "r"(n) : "memory"); }
__device__ __forceinline__ void wgmma_fence() { asm volatile("wgmma.fence.sync.aligned;" ::: "memory"); }
__device__ __forceinline__ void wgmma_commit() { asm volatile("wgmma.commit_group.sync.aligned;" ::: "memory"); }
template <int N>
__device__ __forceinline__ void wgmma_wait() {
    asm volatile("wgmma.wait_group.sync.aligned %0;" ::"n"(N) : "memory");
}
__device__ __forceinline__ void fence_async_smem() { asm volatile("fence.proxy.async.shared::cta;" ::: "memory"); }

__device__ __forceinline__ uint64_t desc_at(uint32_t enc, uint32_t off, uint32_t sbo, uint32_t sw, uint32_t lbo = 0) {
    return (uint64_t)(enc + (off >> 4) + ((lbo >> 4) << 16)) | ((uint64_t)((sbo >> 4) | (sw << 30)) << 32);
}

template <bool FIRST>
__device__ __forceinline__ void wgmma_rs_n64(float* d, const uint32_t* a, uint64_t bdesc) {
    if (FIRST)
        asm volatile("wgmma.mma_async.sync.aligned.m64n64k16.f32.bf16.bf16 {%0,%1,%2,%3,%4,%5,%6,%7,%8,%9,%10,%11,%12,%13,%14,%15,%16,%17,%18,%19,%20,%21,%22,%23,%24,%25,%26,%27,%28,%29,%30,%31}, {%32,%33,%34,%35}, %36, 0, 1, 1, 1;\n"
                     : "=f"(d[0]), "=f"(d[1]), "=f"(d[2]), "=f"(d[3]), "=f"(d[4]), "=f"(d[5]), "=f"(d[6]), "=f"(d[7]), "=f"(d[8]), "=f"(d[9]), "=f"(d[10]), "=f"(d[11]), "=f"(d[12]), "=f"(d[13]), "=f"(d[14]), "=f"(d[15]), "=f"(d[16]), "=f"(d[17]), "=f"(d[18]), "=f"(d[19]), "=f"(d[20]), "=f"(d[21]), "=f"(d[22]), "=f"(d[23]), "=f"(d[24]), "=f"(d[25]), "=f"(d[26]), "=f"(d[27]), "=f"(d[28]), "=f"(d[29]), "=f"(d[30]), "=f"(d[31])
                     : "r"(a[0]), "r"(a[1]), "r"(a[2]), "r"(a[3]), "l"(bdesc));
    else
        asm volatile("wgmma.mma_async.sync.aligned.m64n64k16.f32.bf16.bf16 {%0,%1,%2,%3,%4,%5,%6,%7,%8,%9,%10,%11,%12,%13,%14,%15,%16,%17,%18,%19,%20,%21,%22,%23,%24,%25,%26,%27,%28,%29,%30,%31}, {%32,%33,%34,%35}, %36, 1, 1, 1, 1;\n"
                     : "+f"(d[0]), "+f"(d[1]), "+f"(d[2]), "+f"(d[3]), "+f"(d[4]), "+f"(d[5]), "+f"(d[6]), "+f"(d[7]), "+f"(d[8]), "+f"(d[9]), "+f"(d[10]), "+f"(d[11]), "+f"(d[12]), "+f"(d[13]), "+f"(d[14]), "+f"(d[15]), "+f"(d[16]), "+f"(d[17]), "+f"(d[18]), "+f"(d[19]), "+f"(d[20]), "+f"(d[21]), "+f"(d[22]), "+f"(d[23]), "+f"(d[24]), "+f"(d[25]), "+f"(d[26]), "+f"(d[27]), "+f"(d[28]), "+f"(d[29]), "+f"(d[30]), "+f"(d[31])
                     : "r"(a[0]), "r"(a[1]), "r"(a[2]), "r"(a[3]), "l"(bdesc));
}
template <bool FIRST>
__device__ __forceinline__ void wgmma_rs_n96(float* d, const uint32_t* a, uint64_t bdesc) {
    if (FIRST)
        asm volatile("wgmma.mma_async.sync.aligned.m64n96k16.f32.bf16.bf16 {%0,%1,%2,%3,%4,%5,%6,%7,%8,%9,%10,%11,%12,%13,%14,%15,%16,%17,%18,%19,%20,%21,%22,%23,%24,%25,%26,%27,%28,%29,%30,%31,%32,%33,%34,%35,%36,%37,%38,%39,%40,%41,%42,%43,%44,%45,%46,%47}, {%48,%49,%50,%51}, %52, 0, 1, 1, 1;\n"
                     : "=f"(d[0]), "=f"(d[1]), "=f"(d[2]), "=f"(d[3]), "=f"(d[4]), "=f"(d[5]), "=f"(d[6]), "=f"(d[7]), "=f"(d[8]), "=f"(d[9]), "=f"(d[10]), "=f"(d[11]), "=f"(d[12]), "=f"(d[13]), "=f"(d[14]), "=f"(d[15]), "=f"(d[16]), "=f"(d[17]), "=f"(d[18]), "=f"(d[19]), "=f"(d[20]), "=f"(d[21]), "=f"(d[22]), "=f"(d[23]), "=f"(d[24]), "=f"(d[25]), "=f"(d[26]), "=f"(d[27]), "=f"(d[28]), "=f"(d[29]), "=f"(d[30]), "=f"(d[31]), "=f"(d[32]), "=f"(d[33]), "=f"(d[34]), "=f"(d[35]), "=f"(d[36]), "=f"(d[37]), "=f"(d[38]), "=f"(d[39]), "=f"(d[40]), "=f"(d[41]), "=f"(d[42]), "=f"(d[43]), "=f"(d[44]), "=f"(d[45]), "=f"(d[46]), "=f"(d[47])
                     : "r"(a[0]), "r"(a[1]), "r"(a[2]), "r"(a[3]), "l"(bdesc));
    else
        asm volatile("wgmma.mma_async.sync.aligned.m64n96k16.f32.bf16.bf16 {%0,%1,%2,%3,%4,%5,%6,%7,%8,%9,%10,%11,%12,%13,%14,%15,%16,%17,%18,%19,%20,%21,%22,%23,%24,%25,%26,%27,%28,%29,%30,%31,%32,%33,%34,%35,%36,%37,%38,%39,%40,%41,%42,%43,%44,%45,%46,%47}, {%48,%49,%50,%51}, %52, 1, 1, 1, 1;\n"
                     : "+f"(d[0]), "+f"(d[1]), "+f"(d[2]), "+f"(d[3]), "+f"(d[4]), "+f"(d[5]), "+f"(d[6]), "+f"(d[7]), "+f"(d[8]), "+f"(d[9]), "+f"(d[10]), "+f"(d[11]), "+f"(d[12]), "+f"(d[13]), "+f"(d[14]), "+f"(d[15]), "+f"(d[16]), "+f"(d[17]), "+f"(d[18]), "+f"(d[19]), "+f"(d[20]), "+f"(d[21]), "+f"(d[22]), "+f"(d[23]), "+f"(d[24]), "+f"(d[25]), "+f"(d[26]), "+f"(d[27]), "+f"(d[28]), "+f"(d[29]), "+f"(d[30]), "+f"(d[31]), "+f"(d[32]), "+f"(d[33]), "+f"(d[34]), "+f"(d[35]), "+f"(d[36]), "+f"(d[37]), "+f"(d[38]), "+f"(d[39]), "+f"(d[40]), "+f"(d[41]), "+f"(d[42]), "+f"(d[43]), "+f"(d[44]), "+f"(d[45]), "+f"(d[46]), "+f"(d[47])
                     : "r"(a[0]), "r"(a[1]), "r"(a[2]), "r"(a[3]), "l"(bdesc));
}
template <bool FIRST>
__device__ __forceinline__ void wgmma_rs_n128(float* d, const uint32_t* a, uint64_t bdesc) {
    if (FIRST)
        asm volatile("wgmma.mma_async.sync.aligned.m64n128k16.f32.bf16.bf16 {%0,%1,%2,%3,%4,%5,%6,%7,%8,%9,%10,%11,%12,%13,%14,%15,%16,%17,%18,%19,%20,%21,%22,%23,%24,%25,%26,%27,%28,%29,%30,%31,%32,%33,%34,%35,%36,%37,%38,%39,%40,%41,%42,%43,%44,%45,%46,%47,%48,%49,%50,%51,%52,%53,%54,%55,%56,%57,%58,%59,%60,%61,%62,%63}, {%64,%65,%66,%67}, %68, 0, 1, 1, 1;\n"
                     : "=f"(d[0]), "=f"(d[1]), "=f"(d[2]), "=f"(d[3]), "=f"(d[4]), "=f"(d[5]), "=f"(d[6]), "=f"(d[7]), "=f"(d[8]), "=f"(d[9]), "=f"(d[10]), "=f"(d[11]), "=f"(d[12]), "=f"(d[13]), "=f"(d[14]), "=f"(d[15]), "=f"(d[16]), "=f"(d[17]), "=f"(d[18]), "=f"(d[19]), "=f"(d[20]), "=f"(d[21]), "=f"(d[22]), "=f"(d[23]), "=f"(d[24]), "=f"(d[25]), "=f"(d[26]), "=f"(d[27]), "=f"(d[28]), "=f"(d[29]), "=f"(d[30]), "=f"(d[31]), "=f"(d[32]), "=f"(d[33]), "=f"(d[34]), "=f"(d[35]), "=f"(d[36]), "=f"(d[37]), "=f"(d[38]), "=f"(d[39]), "=f"(d[40]), "=f"(d[41]), "=f"(d[42]), "=f"(d[43]), "=f"(d[44]), "=f"(d[45]), "=f"(d[46]), "=f"(d[47]), "=f"(d[48]), "=f"(d[49]), "=f"(d[50]), "=f"(d[51]), "=f"(d[52]), "=f"(d[53]), "=f"(d[54]), "=f"(d[55]), "=f"(d[56]), "=f"(d[57]), "=f"(d[58]), "=f"(d[59]), "=f"(d[60]), "=f"(d[61]), "=f"(d[62]), "=f"(d[63])
                     : "r"(a[0]), "r"(a[1]), "r"(a[2]), "r"(a[3]), "l"(bdesc));
    else
        asm volatile("wgmma.mma_async.sync.aligned.m64n128k16.f32.bf16.bf16 {%0,%1,%2,%3,%4,%5,%6,%7,%8,%9,%10,%11,%12,%13,%14,%15,%16,%17,%18,%19,%20,%21,%22,%23,%24,%25,%26,%27,%28,%29,%30,%31,%32,%33,%34,%35,%36,%37,%38,%39,%40,%41,%42,%43,%44,%45,%46,%47,%48,%49,%50,%51,%52,%53,%54,%55,%56,%57,%58,%59,%60,%61,%62,%63}, {%64,%65,%66,%67}, %68, 1, 1, 1, 1;\n"
                     : "+f"(d[0]), "+f"(d[1]), "+f"(d[2]), "+f"(d[3]), "+f"(d[4]), "+f"(d[5]), "+f"(d[6]), "+f"(d[7]), "+f"(d[8]), "+f"(d[9]), "+f"(d[10]), "+f"(d[11]), "+f"(d[12]), "+f"(d[13]), "+f"(d[14]), "+f"(d[15]), "+f"(d[16]), "+f"(d[17]), "+f"(d[18]), "+f"(d[19]), "+f"(d[20]), "+f"(d[21]), "+f"(d[22]), "+f"(d[23]), "+f"(d[24]), "+f"(d[25]), "+f"(d[26]), "+f"(d[27]), "+f"(d[28]), "+f"(d[29]), "+f"(d[30]), "+f"(d[31]), "+f"(d[32]), "+f"(d[33]), "+f"(d[34]), "+f"(d[35]), "+f"(d[36]), "+f"(d[37]), "+f"(d[38]), "+f"(d[39]), "+f"(d[40]), "+f"(d[41]), "+f"(d[42]), "+f"(d[43]), "+f"(d[44]), "+f"(d[45]), "+f"(d[46]), "+f"(d[47]), "+f"(d[48]), "+f"(d[49]), "+f"(d[50]), "+f"(d[51]), "+f"(d[52]), "+f"(d[53]), "+f"(d[54]), "+f"(d[55]), "+f"(d[56]), "+f"(d[57]), "+f"(d[58]), "+f"(d[59]), "+f"(d[60]), "+f"(d[61]), "+f"(d[62]), "+f"(d[63])
                     : "r"(a[0]), "r"(a[1]), "r"(a[2]), "r"(a[3]), "l"(bdesc));
}
__device__ __forceinline__ void mma_16816(float (&c)[4], uint32_t a0, uint32_t a1, uint32_t a2, uint32_t a3, uint32_t b0,
                                          uint32_t b1) {
    asm volatile(
        "mma.sync.aligned.m16n8k16.row.col.f32.bf16.bf16.f32 {%0,%1,%2,%3}, {%4,%5,%6,%7}, {%8,%9}, {%0,%1,%2,%3};"
        : "+f"(c[0]), "+f"(c[1]), "+f"(c[2]), "+f"(c[3])
        : "r"(a0), "r"(a1), "r"(a2), "r"(a3), "r"(b0), "r"(b1));
}
__device__ __forceinline__ void ldmatrix_x4(uint32_t* d, uint32_t addr) {
    asm volatile("ldmatrix.sync.aligned.m8n8.x4.shared.b16 {%0,%1,%2,%3}, [%4];"
                 : "=r"(d[0]), "=r"(d[1]), "=r"(d[2]), "=r"(d[3])
                 : "r"(addr)
                 : "memory");
}

__device__ __forceinline__ uint32_t pack_bf16(float lo, float hi) {
    uint32_t r;
    asm("cvt.rn.bf16x2.f32 %0, %1, %2;" : "=r"(r) : "f"(hi), "f"(lo));
    return r;
}
__device__ __forceinline__ float bf_lo(uint32_t v) { return __uint_as_float(v << 16); }
__device__ __forceinline__ float bf_hi(uint32_t v) { return __uint_as_float(v & 0xffff0000u); }
__device__ __forceinline__ float round_bf16(float v) { return __bfloat162float(__float2bfloat16_rn(v)); }
__device__ __forceinline__ uint32_t bf2_add(uint32_t a, uint32_t b) {
    uint32_t r;
    asm("add.rn.bf16x2 %0, %1, %2;" : "=r"(r) : "r"(a), "r"(b));
    return r;
}
__device__ __forceinline__ uint32_t bf2_sub(uint32_t a, uint32_t b) {
    uint32_t r;
    asm("sub.rn.bf16x2 %0, %1, %2;" : "=r"(r) : "r"(a), "r"(b));
    return r;
}
__device__ __forceinline__ uint32_t bf2_sub_v(uint32_t a, uint32_t b) {
    uint32_t r;
    asm volatile("sub.rn.bf16x2 %0, %1, %2;" : "=r"(r) : "r"(a), "r"(b));
    return r;
}
__device__ __forceinline__ float gelu2_tanh(float u) {
    const float k0 = 0.7978845608028654f, k1 = 0.7978845608028654f * 0.044715f;
    float z = u * fmaf(u * u, k1, k0);
    float t;
    asm("tanh.approx.f32 %0, %1;" : "=f"(t) : "f"(z));
    return fmaf(u, t, u);
}
__device__ __forceinline__ uint32_t gelu_pair(float a0, float a1, float rs, float2 b) {
    return pack_bf16(gelu2_tanh(fmaf(a0, rs, b.x)), gelu2_tanh(fmaf(a1, rs, b.y)));
}
__device__ __forceinline__ void stmatrix_x4(uint32_t addr, uint32_t r0, uint32_t r1, uint32_t r2, uint32_t r3) {
    asm volatile("stmatrix.sync.aligned.m8n8.x4.shared.b16 [%0], {%1,%2,%3,%4};" ::"r"(addr), "r"(r0), "r"(r1), "r"(r2),
                 "r"(r3)
                 : "memory");
}
__device__ __forceinline__ uint32_t lds32(uint32_t addr) {
    uint32_t v;
    asm volatile("ld.shared.b32 %0, [%1];" : "=r"(v) : "r"(addr));
    return v;
}

__device__ __forceinline__ void lds128(uint32_t (&v)[4], uint32_t addr) {
    asm volatile("ld.shared.v4.b32 {%0,%1,%2,%3}, [%4];" : "=r"(v[0]), "=r"(v[1]), "=r"(v[2]), "=r"(v[3]) : "r"(addr) : "memory");
}
constexpr int NB_AUX = 4;
constexpr int NB_END = 5;
constexpr int NSTAGE1 = 16;
constexpr int NSTAGE = NSTAGE1 + 16;

__global__ void __launch_bounds__(384, 1)
mixer_mlp_kernel(const __grid_constant__ CUtensorMap tm_x, const __grid_constant__ CUtensorMap tm_w1,
                 const __grid_constant__ CUtensorMap tm_w2, const __nv_bfloat16* __restrict__ b1,
                 const __nv_bfloat16* __restrict__ b2, __nv_bfloat16* __restrict__ out) {
    extern __shared__ __align__(1024) uint8_t smem[];
    const uint32_t sb = smem_u32(smem);
    const int tid = threadIdx.x;
    const int warp = tid >> 5, lane = tid & 31;
    const int r = blockIdx.x & 1;
    const int f = (blockIdx.x >> 1) & 3;
    const int rt = blockIdx.x >> 3;
    const int grp = rt * 2 + r;
    const uint32_t peer = (uint32_t)(r ^ 1);
    int budget = 1 << 14;
    const int fcol_own = 448 * f + 224 * r;
    const int fcol_peer = 448 * f + 224 * (1 - r);

    if (tid == 256) {
        for (int i = 0; i < 4; i++) mbar_init(sb + BAR_XFULL + 8 * i, 1);
        fence_async_smem();
        for (int kp = 0; kp < 4; kp++) {
            mbar_expect_tx(sb + BAR_XFULL + 8 * kp, 32768);
            tma_2d(sb + (2 * kp) * 16384, &tm_x, sb + BAR_XFULL + 8 * kp, (2 * kp) * 64, rt * 128);
            tma_2d(sb + (2 * kp + 1) * 16384, &tm_x, sb + BAR_XFULL + 8 * kp, (2 * kp + 1) * 64, rt * 128);
        }
    } else if (tid == 288) {
        for (int i = 0; i < NSLOT; i++) {
            mbar_init(sb + BAR_FULL + 8 * i, 1);
            mbar_init(sb + BAR_EMPTY + 8 * i, 8);
        }
        mbar_arrive(sb + BAR_FULL);
        fence_async_smem();
    } else if (tid == 320) {
        for (int i = 0; i < 4; i++) mbar_init(sb + BAR_HFULL + 8 * i, 1);
        for (int i = 0; i < 2; i++) mbar_init(sb + BAR_XFREE + 8 * i, 4);
        mbar_init(sb + BAR_RDY, 1);
        mbar_init(sb + BAR_BIAS, 2);
        for (int i = 0; i < 4; i++) mbar_init(sb + BAR_PUB + 8 * i, 4);
        for (int i = 0; i < 2; i++) mbar_init(sb + BAR_HRECV + 8 * i, 4);
        for (int i = 0; i < 4; i++) mbar_expect_tx(sb + BAR_HFULL + 8 * i, (i >> 1) ? 12288 : 16384);
        asm volatile("fence.mbarrier_init.release.cluster;" ::: "memory");
        fence_async_smem();
    }
    __syncthreads();
    cluster_arrive_relaxed();

    if (warp >= 8) {
        asm volatile("setmaxnreg.dec.sync.aligned.u32 40;");
        if (warp == 8) {
            if (lane == 0) {
                int slot = 1;
                uint32_t ph = 1;
                for (int j = 1; j <= NSTAGE; j++) {
                    if (j == 3) mbar_wait(sb + BAR_XFULL + 16, 0, budget);
                    mbar_wait(sb + BAR_EMPTY + 8 * slot, ph, budget);
                    const uint32_t bar = sb + BAR_FULL + 8 * slot;
                    const uint32_t dst = sb + OFF_RING + slot * SLOT_BYTES;
                    const int s = j - 1;
                    if (s < NSTAGE1) {
                        mbar_expect_tx(bar, 16384);
                        const int c0 = fcol_own + (s >> 3) * 128, k0 = (s & 7) * 64;
                        tma_2d(dst, &tm_w1, bar, c0, k0);
                        tma_2d(dst + 8192, &tm_w1, bar, c0 + 64, k0);
                    } else {
                        const int p = s - NSTAGE1;
                        int pass, peer_k, hi_k;
                        if (p < 4) {
                            pass = p & 1, peer_k = p >> 1, hi_k = 0;
                        } else if (p < 8) {
                            pass = (p >> 1) & 1, peer_k = p & 1, hi_k = 1;
                        } else {
                            pass = p >> 2, peer_k = p & 1, hi_k = (p >> 1) & 1;
                        }
                        const int q = (f + 1 + pass) & 3;
                        const int row = (peer_k ? fcol_peer : fcol_own) + hi_k * 112;
                        mbar_expect_tx(bar, 14336);
                        tma_2d(dst, &tm_w2, bar, 256 * r + 64 * q, row);
                    }
                    if (++slot == NSLOT) {
                        slot = 0;
                        ph ^= 1;
                    }
                }
            }
            __syncwarp();
            cluster_wait();
        } else {
            const int tb = tid - 288;
            if (warp > 9) {
                for (int i = tb - 32; i < 112; i += 64) {
                    const uint32_t bb = reinterpret_cast<const uint32_t*>(b1 + fcol_own)[i];
                    reinterpret_cast<float2*>(smem + OFF_B1)[i] = make_float2(bf_lo(bb), bf_hi(bb));
                }
                if (tb < 64)
                    reinterpret_cast<uint32_t*>(smem + OFF_B2)[tb - 32] =
                        reinterpret_cast<const uint32_t*>(b2 + 256 * r + 64 * f)[tb - 32];
                __syncwarp();
                if (lane == 0) mbar_arrive(sb + BAR_BIAS);
            }
            uint4* inbox = g_part + (size_t)(grp * 4 + f) * 3072;
            for (int i = 0; i < 4; i++) mbar_wait(sb + BAR_XFULL + 8 * i, 0, budget);
            for (int i = tb; i < 3072; i += 96) __stcg(inbox + i, make_uint4(~0u, ~0u, ~0u, ~0u));
            __threadfence();
            bar_sync(NB_AUX, 96);
            cluster_wait();
            if (warp == 9) {
                if (lane == 0)
                    asm volatile("st.release.gpu.global.u32 [%0], %1;" ::"l"(g_ready + grp * 4 + f), "r"(1u) : "memory");
                const unsigned int* fl = g_ready + grp * 4 + ((f + 1 + lane) & 3);
                bool done = lane >= 3;
                while (!__all_sync(0xffffffffu, done)) {
                    unsigned int v = 0;
                    if (!done) asm volatile("ld.acquire.gpu.global.u32 %0, [%1];" : "=r"(v) : "l"(fl) : "memory");
                    done = done || (v != 0);
                    if (__any_sync(0xffffffffu, --budget < 0)) break;
                }
                if (lane == 0) mbar_arrive(sb + BAR_RDY);
            } else if (lane == 0) {
                const int w = warp - 10;
                auto copy_to_peer = [&](uint32_t off_src, uint32_t off_dst, uint32_t bytes, int c) {
                    asm volatile(
                        "cp.async.bulk.shared::cluster.shared::cta.mbarrier::complete_tx::bytes [%0], [%1], %2, [%3];" ::"r"(
                            mapa(sb + off_dst, peer)),
                        "r"(sb + off_src), "r"(bytes), "r"(mapa(sb + BAR_HFULL + 8 * (2 * c + w), peer))
                        : "memory");
                };
                mbar_wait(sb + BAR_XFREE + 8 * w, 0, budget);
                mbar_wait(sb + BAR_PUB + 8 * w, 0, budget);
                copy_to_peer(OFF_H_OWN + w * 8192, OFF_H_PEER + w * 8192, 8192, 0);
                copy_to_peer(OFF_H_OWN + 16384 + w * 8192, OFF_H_PEER + 16384 + w * 8192, 8192, 0);
                mbar_wait(sb + BAR_PUB + 8 * (2 + w), 0, budget);
                copy_to_peer(OFF_H_OWN + 32768 + w * 8192, OFF_H_PEER + 32768 + w * 8192, 8192, 1);
                copy_to_peer(OFF_H_OWN3 + w * 4096, OFF_H_PEER3 + w * 4096, 4096, 1);
                mbar_wait(sb + BAR_HRECV + 8 * w, 0, budget);
            }
        }
    } else {
        asm volatile("setmaxnreg.inc.sync.aligned.u32 232;");
        const int w = warp >> 2;
        const int g = lane >> 2;

        uint32_t y[128];
        float rs0, rs1;
        {
            const uint32_t lrow = (tid >> 5) * 16 + (lane & 15), lane_hi = lane >> 4;
            const uint32_t ld128 = sb + lrow * 128, lx128 = lrow & 7;
            float sm[4] = {0.f, 0.f, 0.f, 0.f}, ga[4] = {0.f, 0.f, 0.f, 0.f}, gb[4] = {0.f, 0.f, 0.f, 0.f};
#pragma unroll
            for (int kp = 0; kp < 4; kp++) {
                mbar_wait(sb + BAR_XFULL + 8 * kp, 0, budget);
#pragma unroll
                for (int kk = 0; kk < 8; kk++) {
                    const int ks = 8 * kp + kk;
                    ldmatrix_x4(&y[4 * ks], ld128 + (ks >> 2) * 16384 + ((((ks & 3) * 2 + lane_hi) ^ lx128) << 4));
                }
#pragma unroll
                for (int kk = 0; kk < 8; kk++) {
                    const int ks = 8 * kp + kk;
                    mma_16816(sm, y[4 * ks], y[4 * ks + 1], y[4 * ks + 2], y[4 * ks + 3], 0x3F803F80u, 0x3F803F80u);
                    mma_16816(ga, y[4 * ks], y[4 * ks + 1], y[4 * ks + 2], y[4 * ks + 3], y[4 * ks], y[4 * ks + 2]);
                    mma_16816(gb, y[4 * ks], y[4 * ks + 1], y[4 * ks + 2], y[4 * ks + 3], y[4 * ks + 1], y[4 * ks + 3]);
                }
            }
            __syncwarp();
            cluster_wait();
            if (lane == 0) {
                mbar_arrive(sb + BAR_EMPTY);
                mbar_arrive_remote(mapa(sb + BAR_XFREE + 8 * w, peer));
            }
            const int srcl = (lane & ~3) | (g >> 1);
            float qa0 = __shfl_sync(0xffffffffu, ga[0], srcl), qa1 = __shfl_sync(0xffffffffu, ga[1], srcl);
            float qb0 = __shfl_sync(0xffffffffu, gb[2], srcl), qb1 = __shfl_sync(0xffffffffu, gb[3], srcl);
            const float m0 = sm[0] * (1.f / DM), m1 = sm[2] * (1.f / DM);
            float v0 = ((g & 1) ? qa1 : qa0) * (1.f / DM) - m0 * m0;
            float v1 = ((g & 1) ? qb1 : qb0) * (1.f / DM) - m1 * m1;
            uint32_t mm0 = pack_bf16(m0, m0), mm1 = pack_bf16(m1, m1);
            if (__any_sync(0xffffffffu, (m0 * m0 > 32.f * v0) || (m1 * m1 > 32.f * v1))) {
#pragma unroll
                for (int i = 0; i < 4; i++) sm[i] = ga[i] = gb[i] = 0.f;
#pragma unroll
                for (int ks = 0; ks < 32; ks++) {
                    const uint32_t d0 = bf2_sub(y[4 * ks], mm0), d1 = bf2_sub(y[4 * ks + 1], mm1);
                    const uint32_t d2 = bf2_sub(y[4 * ks + 2], mm0), d3 = bf2_sub(y[4 * ks + 3], mm1);
                    mma_16816(sm, d0, d1, d2, d3, 0x3F803F80u, 0x3F803F80u);
                    mma_16816(ga, d0, d1, d2, d3, d0, d2);
                    mma_16816(gb, d0, d1, d2, d3, d1, d3);
                }
                qa0 = __shfl_sync(0xffffffffu, ga[0], srcl), qa1 = __shfl_sync(0xffffffffu, ga[1], srcl);
                qb0 = __shfl_sync(0xffffffffu, gb[2], srcl), qb1 = __shfl_sync(0xffffffffu, gb[3], srcl);
                const float e0 = sm[0] * (1.f / DM), e1 = sm[2] * (1.f / DM);
                if (m0 * m0 > 32.f * v0) v0 = fmaxf(((g & 1) ? qa1 : qa0) * (1.f / DM) - e0 * e0, 0.f);
                if (m1 * m1 > 32.f * v1) v1 = fmaxf(((g & 1) ? qb1 : qb0) * (1.f / DM) - e1 * e1, 0.f);
            }
            const float sd0 = round_bf16(sqrtf(round_bf16(round_bf16(v0) + 1e-5f)));
            const float sd1 = round_bf16(sqrtf(round_bf16(round_bf16(v1) + 1e-5f)));
            rs0 = 1.f / sd0;
            rs1 = 1.f / sd1;
#pragma unroll
            for (int i = 0; i < 128; i++) y[i] = bf2_sub_v(y[i], (i & 1) ? mm1 : mm0);
        }

        float acc[64], acc2[32];
        uint32_t hf[112];

        auto wait_full = [&](int j) { mbar_wait(sb + BAR_FULL + 8 * (j % NSLOT), (j / NSLOT) & 1, budget); };
        auto stage_enc = [&](int j) -> uint32_t {
            uint32_t enc;
            asm volatile("shr.u32 %0, %1, 4;" : "=r"(enc) : "r"((sb & 0x3FFFFu) + OFF_RING + (j % NSLOT) * SLOT_BYTES));
            return enc;
        };
        auto release = [&](int j) {
            if (lane == 0) mbar_arrive(sb + BAR_EMPTY + 8 * (j % NSLOT));
        };
        auto end_stage = [&](int j, bool rel_prev, bool drain) {
            wgmma_commit();
            wgmma_wait<1>();
            if (rel_prev) release(j - 1);
            if (drain) {
                wgmma_wait<0>();
                release(j);
            }
        };
        auto gelu_chunk = [&](int c) {
            const uint32_t tn = tid_now(), ln = tn & 31, hi = ln >> 4;
            const uint32_t srow = (tn >> 5) * 16 + (ln & 7) + (ln & 8);
            const uint32_t st128 = sb + OFF_H_OWN + c * 32768 + srow * 128, x128 = srow & 7;
            const float2* bias = reinterpret_cast<const float2*>(smem + OFF_B1) + c * 64 + (ln & 3);
#pragma unroll
            for (int j0 = 0; j0 < (c ? 12 : 16); j0 += 2) {
                const float2 bA = bias[4 * j0], bB = bias[4 * j0 + 4];
                uint32_t tmp[4];
                uint32_t* o = (c == 1) ? &hf[4 * (8 + (j0 >> 1))] : tmp;
                o[0] = gelu_pair(acc[4 * j0 + 0], acc[4 * j0 + 1], rs0, bA);
                o[1] = gelu_pair(acc[4 * j0 + 2], acc[4 * j0 + 3], rs1, bA);
                o[2] = gelu_pair(acc[4 * j0 + 4], acc[4 * j0 + 5], rs0, bB);
                o[3] = gelu_pair(acc[4 * j0 + 6], acc[4 * j0 + 7], rs1, bB);
                uint32_t st;
                if (c == 1 && j0 >= 8)
                    st = sb + OFF_H_OWN3 + srow * 64 + (((j0 - 8 + hi) ^ ((srow >> 1) & 3)) << 4);
                else
                    st = st128 + (j0 >> 3) * 16384 + ((((j0 & 7) + hi) ^ x128) << 4);
                stmatrix_x4(st, o[0], o[1], o[2], o[3]);
            }
        };
        auto publish = [&](int c) {
            fence_async_smem();
            __syncwarp();
            if (lane == 0) mbar_arrive(sb + BAR_PUB + 8 * (2 * c + w));
        };

#pragma unroll
        for (int c = 0; c < 2; c++) {
#pragma unroll
            for (int s = 0; s < 8; s++) {
                const int j = 1 + 8 * c + s;
                wait_full(j);
                wgmma_fence();
                const uint32_t bs = stage_enc(j);
#pragma unroll
                for (int k = 0; k < 4; k++) {
                    const uint64_t bd = desc_at(bs, k * 2048, 1024, 1, 8192);
                    if (c == 0) {
                        if ((s | k) == 0) wgmma_rs_n128<true>(acc, &y[4 * (4 * s + k)], bd);
                        else wgmma_rs_n128<false>(acc, &y[4 * (4 * s + k)], bd);
                    } else {
                        if ((s | k) == 0) wgmma_rs_n96<true>(acc, &y[4 * (4 * s + k)], bd);
                        else wgmma_rs_n96<false>(acc, &y[4 * (4 * s + k)], bd);
                    }
                }
                end_stage(j, s > 0, s == 7);
            }
            if (c == 0) mbar_wait(sb + BAR_BIAS, 0, budget);
            gelu_chunk(c);
            publish(c);
        }

        auto load_h = [&](bool own, int k0, int k1) {
            const uint32_t tn = tid_now(), lane_hi = (tn >> 4) & 1;
            const uint32_t lrow = (tn >> 5) * 16 + (tn & 15);
            const uint32_t ld128 = sb + lrow * 128, lx128 = lrow & 7;
            const uint32_t ld64 = sb + lrow * 64, lx64 = (lrow >> 1) & 3;
#pragma unroll
            for (int kk = k0; kk < k1; kk++) {
                uint32_t addr;
                if (kk < 12)
                    addr = ld128 + (own ? OFF_H_OWN : OFF_H_PEER) + (kk >> 2) * 16384 +
                           ((((kk & 3) * 2 + lane_hi) ^ lx128) << 4);
                else
                    addr = ld64 + (own ? OFF_H_OWN3 : OFF_H_PEER3) + ((((kk & 1) * 2 + lane_hi) ^ lx64) << 4);
                ldmatrix_x4(&hf[4 * ((own ? 0 : 14) + kk)], addr);
            }
        };
        auto send = [&](int i, const float* a) {
            const int q = (f + 1 + i) & 3;
            const uint32_t tn = tid_now();
            uint4* dst = g_part + (size_t)((grp * 4 + q) * 3 + i) * 1024 + (tn >> 7) * 512 + (tn & 127);
#pragma unroll
            for (int e = 0; e < 4; e++)
                __stcg(dst + e * 128, make_uint4(pack_bf16(a[8 * e], a[8 * e + 1]), pack_bf16(a[8 * e + 2], a[8 * e + 3]),
                                                 pack_bf16(a[8 * e + 4], a[8 * e + 5]), pack_bf16(a[8 * e + 6], a[8 * e + 7])));
        };
        load_h(true, 0, 8);
        uint32_t v[48];
        const uint32_t tn = tid_now(), ln = tn & 31;
        const uint4* inbox = g_part + (size_t)(grp * 4 + f) * 3072 + (tn >> 7) * 512 + (tn & 127);
        auto ld_slot = [&](int i) {
#pragma unroll
            for (int e = 0; e < 4; e++)
                asm volatile("ld.relaxed.gpu.global.v4.b32 {%0,%1,%2,%3}, [%4];"
                             : "=r"(v[16 * i + 4 * e]), "=r"(v[16 * i + 4 * e + 1]), "=r"(v[16 * i + 4 * e + 2]),
                               "=r"(v[16 * i + 4 * e + 3])
                             : "l"(inbox + i * 1024 + e * 128)
                             : "memory");
        };
#pragma unroll
        for (int p = 0; p < 16; p++) {
            const int j = NSTAGE1 + 1 + p;
            const int pass = (p < 4) ? (p & 1) : (p < 8) ? ((p >> 1) & 1) : (p >> 2);
            const int peer_k = (p < 4) ? (p >> 1) : (p & 1);
            const int hi_k = (p < 4) ? 0 : (p < 8) ? 1 : ((p >> 1) & 1);
            const bool first = (p < 2) || p == 8 || p == 12;
            if (p == 2) {
                mbar_wait(sb + BAR_RDY, 0, budget);
                mbar_wait(sb + BAR_HFULL + 8 * (0 + w), 0, budget);
                load_h(false, 0, 7);
            }
            if (p == 5) {
                mbar_wait(sb + BAR_HFULL + 8 * (2 + w), 0, budget);
                if (lane == 0) mbar_arrive_remote(mapa(sb + BAR_HRECV + 8 * w, peer));
                load_h(false, 7, 14);
            }
            wait_full(j);
            wgmma_fence();
            const uint32_t bs = stage_enc(j);
#pragma unroll
            for (int k = 0; k < 7; k++) {
                const uint32_t* af = &hf[4 * (peer_k * 14 + hi_k * 7 + k)];
                if (first && k == 0) wgmma_rs_n64<true>((pass & 1) ? acc2 : acc, af, desc_at(bs, k * 2048, 1024, 1));
                else wgmma_rs_n64<false>((pass & 1) ? acc2 : acc, af, desc_at(bs, k * 2048, 1024, 1));
            }
            if (p == 15) {
                ld_slot(0);
                ld_slot(1);
                ld_slot(2);
            }
            end_stage(j, p != 0, p == 15);
            if (p == 6) send(0, acc);
            if (p == 8) send(1, acc2);
            if (p == 12) send(2, acc);
        }

#pragma unroll
        for (int i = 0; i < 3; i++) {
            while (true) {
                bool ok = true;
#pragma unroll
                for (int z = 0; z < 16; z++) ok = ok && (v[16 * i + z] != ~0u);
                if (ok || --budget < 0) break;
                ld_slot(i);
            }
#pragma unroll
            for (int z = 0; z < 16; z++) {
                acc2[2 * z] += bf_lo(v[16 * i + z]);
                acc2[2 * z + 1] += bf_hi(v[16 * i + z]);
            }
        }
        {
            const uint32_t b2a = sb + OFF_B2 + 4 * (ln & 3);
            const uint32_t srow = (tn >> 5) * 16 + (ln & 7) + (ln & 8), hi = ln >> 4;
            const uint32_t ot = sb + OFF_H_PEER;
#pragma unroll
            for (int j0 = 0; j0 < 8; j0 += 2) {
                const uint32_t bA = lds32(b2a + j0 * 16), bB = lds32(b2a + j0 * 16 + 16);
                stmatrix_x4(ot + srow * 128 + (((j0 + hi) ^ (srow & 7)) << 4),
                            bf2_add(pack_bf16(0.5f * acc2[4 * j0], 0.5f * acc2[4 * j0 + 1]), bA),
                            bf2_add(pack_bf16(0.5f * acc2[4 * j0 + 2], 0.5f * acc2[4 * j0 + 3]), bA),
                            bf2_add(pack_bf16(0.5f * acc2[4 * j0 + 4], 0.5f * acc2[4 * j0 + 5]), bB),
                            bf2_add(pack_bf16(0.5f * acc2[4 * j0 + 6], 0.5f * acc2[4 * j0 + 7]), bB));
            }
            __syncwarp();
            const uint32_t oc = ln & 7;
#pragma unroll
            for (int e = 0; e < 4; e++) {
                const uint32_t rr = (tn >> 5) * 16 + (ln >> 3) + 4 * e;
                uint32_t v[4];
                lds128(v, ot + rr * 128 + ((oc ^ (rr & 7)) << 4));
                *reinterpret_cast<uint4*>(out + (size_t)(rt * 128 + rr) * DM + 256 * r + 64 * f + 8 * oc) =
                    make_uint4(v[0], v[1], v[2], v[3]);
            }
        }
        bar_sync(NB_END, 256);
        if (tn == 0) asm volatile("st.relaxed.gpu.global.u32 [%0], %1;" ::"l"(g_ready + grp * 4 + f), "r"(0u) : "memory");
    }
}

typedef CUresult (*EncodeFn)(CUtensorMap*, CUtensorMapDataType, cuuint32_t, void*, const cuuint64_t*, const cuuint64_t*,
                             const cuuint32_t*, const cuuint32_t*, CUtensorMapInterleave, CUtensorMapSwizzle,
                             CUtensorMapL2promotion, CUtensorMapFloatOOBfill);

}

extern "C" void kernel_launch(void* const* d_in, const int* in_sizes, int n_in, void* d_out, int out_size) {
    (void)in_sizes;
    (void)n_in;
    (void)out_size;
    static EncodeFn enc = nullptr;
    if (!enc) {
        void* fn = nullptr;
        cudaDriverEntryPointQueryResult st;
        cudaGetDriverEntryPoint("cuTensorMapEncodeTiled", &fn, cudaEnableDefault, &st);
        enc = (EncodeFn)fn;
        cudaFuncSetAttribute(mixer_mlp_kernel, cudaFuncAttributeMaxDynamicSharedMemorySize, SMEM_TOTAL);
    }
    void* x = d_in[0];
    void* w1 = d_in[1];
    const __nv_bfloat16* b1 = (const __nv_bfloat16*)d_in[2];
    void* w2 = d_in[3];
    const __nv_bfloat16* b2 = (const __nv_bfloat16*)d_in[4];

    CUtensorMap tm_x, tm_w1, tm_w2;
    cuuint32_t es[2] = {1, 1};
    {
        cuuint64_t gd[2] = {(cuuint64_t)DM, (cuuint64_t)SEQ};
        cuuint64_t gs[1] = {(cuuint64_t)DM * 2};
        cuuint32_t bd[2] = {64, 128};
        enc(&tm_x, CU_TENSOR_MAP_DATA_TYPE_BFLOAT16, 2, x, gd, gs, bd, es, CU_TENSOR_MAP_INTERLEAVE_NONE,
            CU_TENSOR_MAP_SWIZZLE_128B, CU_TENSOR_MAP_L2_PROMOTION_L2_256B, CU_TENSOR_MAP_FLOAT_OOB_FILL_NONE);
    }
    {
        cuuint64_t gd[2] = {(cuuint64_t)FF, (cuuint64_t)DM};
        cuuint64_t gs[1] = {(cuuint64_t)FF * 2};
        cuuint32_t bd[2] = {64, 64};
        enc(&tm_w1, CU_TENSOR_MAP_DATA_TYPE_BFLOAT16, 2, w1, gd, gs, bd, es, CU_TENSOR_MAP_INTERLEAVE_NONE,
            CU_TENSOR_MAP_SWIZZLE_128B, CU_TENSOR_MAP_L2_PROMOTION_L2_128B, CU_TENSOR_MAP_FLOAT_OOB_FILL_NONE);
    }
    {
        cuuint64_t gd[2] = {(cuuint64_t)DM, (cuuint64_t)FF};
        cuuint64_t gs[1] = {(cuuint64_t)DM * 2};
        cuuint32_t bd[2] = {64, 112};
        enc(&tm_w2, CU_TENSOR_MAP_DATA_TYPE_BFLOAT16, 2, w2, gd, gs, bd, es, CU_TENSOR_MAP_INTERLEAVE_NONE,
            CU_TENSOR_MAP_SWIZZLE_128B, CU_TENSOR_MAP_L2_PROMOTION_L2_128B, CU_TENSOR_MAP_FLOAT_OOB_FILL_NONE);
    }

    cudaLaunchConfig_t cfg = {};
    cfg.gridDim = dim3(128);
    cfg.blockDim = dim3(384);
    cfg.dynamicSmemBytes = SMEM_TOTAL;
    cfg.stream = cudaStreamPerThread;
    cudaLaunchAttribute at[1];
    at[0].id = cudaLaunchAttributeClusterDimension;
    at[0].val.clusterDim.x = 2;
    at[0].val.clusterDim.y = 1;
    at[0].val.clusterDim.z = 1;
    cfg.attrs = at;
    cfg.numAttrs = 1;
    cudaLaunchKernelEx(&cfg, mixer_mlp_kernel, tm_x, tm_w1, tm_w2, b1, b2, (__nv_bfloat16*)d_out);
}
```
